```python
import torch

def _softmax(x, axis=-1):
    return torch.softmax(x, dim=axis)
def _gelu(x):
    return torch.nn.functional.gelu(x, approximate="tanh")
def _silu(x):
    return torch.nn.functional.silu(x)
def _sigmoid(x):
    return torch.sigmoid(x)
def _layernorm(x, axis=-1, eps=1e-5):
    m = x.mean(dim=axis, keepdim=True)
    v = x.var(dim=axis, keepdim=True, unbiased=False)
    return (x - m) / torch.sqrt(v + eps)
def _scatter_add(tgt, idx, src, axis=0):
    return tgt.clone().index_add_(axis, idx, src)
def _segment_sum(src, seg, n):
    out = torch.zeros((n,) + src.shape[1:], dtype=src.dtype)
    return out.index_add_(0, seg, src)
def _pad(x, pw):
    flat = tuple(v for pair in reversed(pw) for v in pair)
    return torch.nn.functional.pad(x, flat)

kernel_name = 'concat_heads__mha_block_cached__gqa_block_cached__near_ridge'

def setup_inputs():

    _w = (lambda a: (lambda t: t.to(torch.bfloat16) if t.is_floating_point() else t)(torch.as_tensor(a)))
    def _A_setup():
        B, Sq, D = 8, 128, 512
        H, Sk, Dh = 32, 1024, 128
        return {
            "x": _w((lambda *s: torch.randn(*s, dtype=torch.bfloat16) * 0.8)(B, Sq, D)),
            "k_cache": _w((lambda *s: torch.randn(*s, dtype=torch.bfloat16) * 0.8)(B, H, Sk, Dh)),
            "v_cache": _w((lambda *s: torch.randn(*s, dtype=torch.bfloat16) * 0.05)(B, H, Sk, Dh)),
            "wq": _w((lambda *s: torch.randn(*s, dtype=torch.bfloat16) * 0.8)(D, H * Dh) * (D ** -0.5)),
            "wo": _w((lambda *s: torch.randn(*s, dtype=torch.bfloat16) * 0.05)(H * Dh, D) * ((H * Dh) ** -0.5)),
        }
    _A_in = _A_setup()

    def _B_setup():
        B, Sq, D = 8, 128, 512
        Hq, Hkv, Sk, Dh = 32, 32, 1024, 128
        assert Hq % Hkv == 0, (Hq, Hkv)
        return {
            "x": _w((lambda *s: torch.randn(*s, dtype=torch.bfloat16) * 0.8)(B, Sq, D)),
            "k_cache": _w((lambda *s: torch.randn(*s, dtype=torch.bfloat16) * 0.8)(B, Hkv, Sk, Dh)),
            "v_cache": _w((lambda *s: torch.randn(*s, dtype=torch.bfloat16) * 0.05)(B, Hkv, Sk, Dh)),
            "wq": _w((lambda *s: torch.randn(*s, dtype=torch.bfloat16) * 0.8)(D, Hq * Dh) * (D ** -0.5)),
            "wo": _w((lambda *s: torch.randn(*s, dtype=torch.bfloat16) * 0.05)(Hq * Dh, D) * ((Hq * Dh) ** -0.5)),
        }
    _B_in = _B_setup()

    return {
        "A_x": _A_in["x"],
        "A_k_cache": _A_in["k_cache"],
        "A_v_cache": _A_in["v_cache"],
        "A_wq": _A_in["wq"],
        "A_wo": _A_in["wo"],
        "B_x": _B_in["x"],
        "B_k_cache": _B_in["k_cache"],
        "B_v_cache": _B_in["v_cache"],
        "B_wq": _B_in["wq"],
        "B_wo": _B_in["wo"],
    }

def reference(A_x, A_k_cache, A_v_cache, A_wq, A_wo, B_x, B_k_cache, B_v_cache, B_wq, B_wo):
    def _A_ref(x, k_cache, v_cache, wq, wo):
        B, Sq, D = x.shape
        H, Dh = 32, 128
        q = (lambda x, *d: x.permute(*d))((x @ wq).reshape(B, Sq, H, Dh), 0, 2, 1, 3)
        scores = torch.einsum("bhqd,bhkd->bhqk", q, k_cache) * (Dh ** -0.5)
        p = _softmax(scores, axis=-1)
        o = torch.einsum("bhqk,bhkd->bhqd", p, v_cache)
        return (lambda x, *d: x.permute(*d))(o, 0, 2, 1, 3).reshape(B, Sq, H * Dh) @ wo

    def _B_ref(x, k_cache, v_cache, wq, wo):
        B, Sq, D = x.shape
        Hq, Dh = 32, 128
        Hkv = k_cache.shape[1]
        rep = Hq // Hkv
        q = (lambda x, *d: x.permute(*d))((x @ wq).reshape(B, Sq, Hq, Dh), 0, 2, 1, 3)
        k = (lambda x, n, axis: torch.repeat_interleave(x, n, dim=axis))(k_cache, rep, axis=1)
        v = (lambda x, n, axis: torch.repeat_interleave(x, n, dim=axis))(v_cache, rep, axis=1)
        scores = torch.einsum("bhqd,bhkd->bhqk", q, k) * (Dh ** -0.5)
        p = _softmax(scores, axis=-1)
        o = torch.einsum("bhqk,bhkd->bhqd", p, v)
        return (lambda x, *d: x.permute(*d))(o, 0, 2, 1, 3).reshape(B, Sq, Hq * Dh) @ wo

    a = _A_ref(A_x, A_k_cache, A_v_cache, A_wq, A_wo)
    b = _B_ref(B_x, B_k_cache, B_v_cache, B_wq, B_wo)
    return torch.concatenate([a, b], axis=-1)
```

```cpp
#include <cuda_runtime.h>
#include <cuda_bf16.h>
#include <cuda.h>
#include <stdint.h>

namespace {

constexpr int NB = 8, SQ = 128, DM = 512, NH = 32, SK = 1024, DH = 128;
constexpr int HD = NH * DH;
constexpr int ROWS = NB * SQ;
constexpr int TILE_BYTES = 128 * 128 * 2;
constexpr int HALF_BYTES = 128 * 64 * 2;
constexpr int NKV = 6;
constexpr int PF_TILES = 0;
constexpr int NS2 = 6;
constexpr int STG_BYTES = 128 * 128 * 2;

__device__ __nv_bfloat16 g_o_scratch[(size_t)2 * ROWS * HD];

__device__ __forceinline__ uint32_t smem_u32(const void* p) { return (uint32_t)__cvta_generic_to_shared(p); }

__device__ __forceinline__ void mbar_init(uint32_t bar, uint32_t count) {
    asm volatile("mbarrier.init.shared::cta.b64 [%0], %1;" ::"r"(bar), "r"(count) : "memory");
}
__device__ __forceinline__ void mbar_expect_tx(uint32_t bar, uint32_t bytes) {
    asm volatile("mbarrier.arrive.expect_tx.shared::cta.b64 _, [%0], %1;" ::"r"(bar), "r"(bytes) : "memory");
}
__device__ __forceinline__ void mbar_arrive(uint32_t bar) {
    asm volatile("mbarrier.arrive.shared::cta.b64 _, [%0];" ::"r"(bar) : "memory");
}
__device__ __forceinline__ uint32_t mbar_try_wait(uint32_t bar, uint32_t parity) {
    uint32_t ok;
    asm volatile("{\n\t.reg .pred p;\n\tmbarrier.try_wait.parity.shared::cta.b64 p, [%1], %2;\n\tselp.u32 %0, 1, 0, p;\n\t}"
                 : "=r"(ok) : "r"(bar), "r"(parity) : "memory");
    return ok;
}
__device__ __forceinline__ void mbar_wait(uint32_t bar, uint32_t parity) {
    for (uint32_t spins = 0; !mbar_try_wait(bar, parity) && spins < (1u << 22); ++spins) {}
}
__device__ __forceinline__ void tma_load_2d(uint32_t dst, const CUtensorMap* map, uint32_t bar, int c0, int c1) {
    asm volatile("cp.async.bulk.tensor.2d.shared::cluster.global.mbarrier::complete_tx::bytes [%0], [%1, {%3, %4}], [%2];"
                 ::"r"(dst), "l"(map), "r"(bar), "r"(c0), "r"(c1) : "memory");
}
__device__ __forceinline__ void tma_load_2d_hint(uint32_t dst, const CUtensorMap* map, uint32_t bar, int c0, int c1, uint64_t pol) {
    asm volatile("cp.async.bulk.tensor.2d.shared::cluster.global.mbarrier::complete_tx::bytes.L2::cache_hint [%0], [%1, {%3, %4}], [%2], %5;"
                 ::"r"(dst), "l"(map), "r"(bar), "r"(c0), "r"(c1), "l"(pol) : "memory");
}
__device__ __forceinline__ void tma_prefetch_2d(const CUtensorMap* map, int c0, int c1) {
    asm volatile("cp.async.bulk.prefetch.tensor.2d.L2.global.tile [%0, {%1, %2}];" ::"l"(map), "r"(c0), "r"(c1) : "memory");
}
__device__ __forceinline__ void tma_store_2d(const CUtensorMap* map, uint32_t src, int c0, int c1) {
    asm volatile("cp.async.bulk.tensor.2d.global.shared::cta.bulk_group [%0, {%2, %3}], [%1];"
                 ::"l"(map), "r"(src), "r"(c0), "r"(c1) : "memory");
}
__device__ __forceinline__ void bulk_commit() { asm volatile("cp.async.bulk.commit_group;" ::: "memory"); }
__device__ __forceinline__ void bulk_wait_read0() { asm volatile("cp.async.bulk.wait_group.read 0;" ::: "memory"); }
__device__ __forceinline__ void bulk_wait0() { asm volatile("cp.async.bulk.wait_group 0;" ::: "memory"); }
__device__ __forceinline__ void fence_proxy_async() { asm volatile("fence.proxy.async.shared::cta;" ::: "memory"); }
__device__ __forceinline__ void named_bar_sync(int id, int n) { asm volatile("bar.sync %0, %1;" ::"r"(id), "r"(n) : "memory"); }

__device__ __forceinline__ void wgmma_fence() { asm volatile("wgmma.fence.sync.aligned;" ::: "memory"); }
__device__ __forceinline__ void wgmma_commit() { asm volatile("wgmma.commit_group.sync.aligned;" ::: "memory"); }
template <int N> __device__ __forceinline__ void wgmma_wait() { asm volatile("wgmma.wait_group.sync.aligned %0;" ::"n"(N) : "memory"); }

__device__ __forceinline__ uint64_t make_desc(uint32_t saddr, uint32_t lbo_bytes, uint32_t sbo_bytes) {
    uint64_t d = 0;
    d |= (uint64_t)((saddr & 0x3FFFFu) >> 4);
    d |= (uint64_t)((lbo_bytes & 0x3FFFFu) >> 4) << 16;
    d |= (uint64_t)((sbo_bytes & 0x3FFFFu) >> 4) << 32;
    d |= (uint64_t)1 << 62;
    return d;
}

#define ACC64(a) \
    "+f"(a[0]), "+f"(a[1]), "+f"(a[2]), "+f"(a[3]), "+f"(a[4]), "+f"(a[5]), "+f"(a[6]), "+f"(a[7]), \
    "+f"(a[8]), "+f"(a[9]), "+f"(a[10]), "+f"(a[11]), "+f"(a[12]), "+f"(a[13]), "+f"(a[14]), "+f"(a[15]), \
    "+f"(a[16]), "+f"(a[17]), "+f"(a[18]), "+f"(a[19]), "+f"(a[20]), "+f"(a[21]), "+f"(a[22]), "+f"(a[23]), \
    "+f"(a[24]), "+f"(a[25]), "+f"(a[26]), "+f"(a[27]), "+f"(a[28]), "+f"(a[29]), "+f"(a[30]), "+f"(a[31]), \
    "+f"(a[32]), "+f"(a[33]), "+f"(a[34]), "+f"(a[35]), "+f"(a[36]), "+f"(a[37]), "+f"(a[38]), "+f"(a[39]), \
    "+f"(a[40]), "+f"(a[41]), "+f"(a[42]), "+f"(a[43]), "+f"(a[44]), "+f"(a[45]), "+f"(a[46]), "+f"(a[47]), \
    "+f"(a[48]), "+f"(a[49]), "+f"(a[50]), "+f"(a[51]), "+f"(a[52]), "+f"(a[53]), "+f"(a[54]), "+f"(a[55]), \
    "+f"(a[56]), "+f"(a[57]), "+f"(a[58]), "+f"(a[59]), "+f"(a[60]), "+f"(a[61]), "+f"(a[62]), "+f"(a[63])

#define ACC64_STR \
    "{%0, %1, %2, %3, %4, %5, %6, %7, %8, %9, %10, %11, %12, %13, %14, %15, " \
    "%16, %17, %18, %19, %20, %21, %22, %23, %24, %25, %26, %27, %28, %29, %30, %31, " \
    "%32, %33, %34, %35, %36, %37, %38, %39, %40, %41, %42, %43, %44, %45, %46, %47, " \
    "%48, %49, %50, %51, %52, %53, %54, %55, %56, %57, %58, %59, %60, %61, %62, %63}"

template <int TRANSB>
__device__ __forceinline__ void wgmma_ss(float (&d)[64], uint64_t da, uint64_t db, int scale_d) {
    asm volatile("{\n\t.reg .pred p;\n\tsetp.ne.b32 p, %66, 0;\n\t"
                 "wgmma.mma_async.sync.aligned.m64n128k16.f32.bf16.bf16 " ACC64_STR ", %64, %65, p, 1, 1, 0, %67;\n\t}"
                 : ACC64(d) : "l"(da), "l"(db), "r"(scale_d), "n"(TRANSB));
}
template <int TRANSB>
__device__ __forceinline__ void wgmma_rs(float (&d)[64], uint32_t a0, uint32_t a1, uint32_t a2, uint32_t a3, uint64_t db, int scale_d) {
    asm volatile("{\n\t.reg .pred p;\n\tsetp.ne.b32 p, %69, 0;\n\t"
                 "wgmma.mma_async.sync.aligned.m64n128k16.f32.bf16.bf16 " ACC64_STR ", {%64, %65, %66, %67}, %68, p, 1, 1, %70;\n\t}"
                 : ACC64(d) : "r"(a0), "r"(a1), "r"(a2), "r"(a3), "l"(db), "r"(scale_d), "n"(TRANSB));
}
__device__ __forceinline__ void wgmma_ss_n64(float (&d)[32], uint64_t da, uint64_t db, int scale_d) {
    asm volatile("{\n\t.reg .pred p;\n\tsetp.ne.b32 p, %34, 0;\n\t"
                 "wgmma.mma_async.sync.aligned.m64n64k16.f32.bf16.bf16 {%0, %1, %2, %3, %4, %5, %6, %7, %8, %9, %10, %11, %12, %13, %14, %15, "
                 "%16, %17, %18, %19, %20, %21, %22, %23, %24, %25, %26, %27, %28, %29, %30, %31}, %32, %33, p, 1, 1, 0, 1;\n\t}"
                 : "+f"(d[0]), "+f"(d[1]), "+f"(d[2]), "+f"(d[3]), "+f"(d[4]), "+f"(d[5]), "+f"(d[6]), "+f"(d[7]),
                   "+f"(d[8]), "+f"(d[9]), "+f"(d[10]), "+f"(d[11]), "+f"(d[12]), "+f"(d[13]), "+f"(d[14]), "+f"(d[15]),
                   "+f"(d[16]), "+f"(d[17]), "+f"(d[18]), "+f"(d[19]), "+f"(d[20]), "+f"(d[21]), "+f"(d[22]), "+f"(d[23]),
                   "+f"(d[24]), "+f"(d[25]), "+f"(d[26]), "+f"(d[27]), "+f"(d[28]), "+f"(d[29]), "+f"(d[30]), "+f"(d[31])
                 : "l"(da), "l"(db), "r"(scale_d));
}
__device__ __forceinline__ void fence_acc(float (&d)[64]) {
#pragma unroll
    for (int i = 0; i < 64; i++) asm volatile("" : "+f"(d[i])::"memory");
}
__device__ __forceinline__ void fence_regs(uint32_t (&d)[32]) {
#pragma unroll
    for (int i = 0; i < 32; i++) asm volatile("" : "+r"(d[i])::"memory");
}
__device__ __forceinline__ uint32_t pack_bf16(float lo, float hi) {
    uint32_t r;
    asm("cvt.rn.bf16x2.f32 %0, %1, %2;" : "=r"(r) : "f"(hi), "f"(lo));
    return r;
}
__device__ __forceinline__ float ex2(float x) { float y; asm("ex2.approx.ftz.f32 %0, %1;" : "=f"(y) : "f"(x)); return y; }
__device__ __forceinline__ void stmatrix_x4(uint32_t addr, uint32_t r0, uint32_t r1, uint32_t r2, uint32_t r3) {
    asm volatile("stmatrix.sync.aligned.m8n8.x4.shared.b16 [%0], {%1, %2, %3, %4};" ::"r"(addr), "r"(r0), "r"(r1), "r"(r2), "r"(r3) : "memory");
}

__device__ __forceinline__ void store_tile(float (&o)[64], float s0, float s1, uint32_t stg, const CUtensorMap* map,
                                           int col0, int row0, int wg_bar, int lane, int warp_in_wg, bool elected) {
    if (elected) bulk_wait_read0();
    named_bar_sync(wg_bar, 128);
    const int mi = lane >> 3;
    const int row = warp_in_wg * 16 + (mi & 1) * 8 + (lane & 7);
#pragma unroll
    for (int j = 0; j < 16; j += 2) {
        uint32_t r0 = pack_bf16(o[4 * j + 0] * s0, o[4 * j + 1] * s0);
        uint32_t r1 = pack_bf16(o[4 * j + 2] * s1, o[4 * j + 3] * s1);
        uint32_t r2 = pack_bf16(o[4 * j + 4] * s0, o[4 * j + 5] * s0);
        uint32_t r3 = pack_bf16(o[4 * j + 6] * s1, o[4 * j + 7] * s1);
        const int cb = j + (mi >> 1);
        const int half = cb >> 3, c = cb & 7;
        uint32_t addr = stg + half * 8192 + row * 128 + ((c ^ (row & 7)) << 4);
        stmatrix_x4(addr, r0, r1, r2, r3);
    }
    fence_proxy_async();
    named_bar_sync(wg_bar, 128);
    if (elected) {
        tma_store_2d(map, stg, col0, row0);
        tma_store_2d(map, stg + 8192, col0 + 64, row0);
        bulk_commit();
    }
}

struct Maps1 {
    CUtensorMap x[2], wq[2], k[2], v[2], o;
};

__global__ void __launch_bounds__(384, 1) attn_kernel(const __grid_constant__ Maps1 maps) {
    extern __shared__ uint8_t smem_raw[];
    const uint32_t smem_base = (smem_u32(smem_raw) + 1023u) & ~1023u;
    const uint32_t ring = smem_base;
    const uint32_t stg_base = ring + NKV * TILE_BYTES;
    const uint32_t bars = stg_base + STG_BYTES;
    const int tid = threadIdx.x, wg = tid >> 7, lane = tid & 31, warp = tid >> 5;

    if (tid == 0) {
        for (int s = 0; s < NKV; s++) { mbar_init(bars + 8 * s, 1); mbar_init(bars + 8 * (NKV + s), 8); }
        asm volatile("fence.mbarrier_init.release.cluster;" ::: "memory");
    }
    __syncthreads();
    const int blk = blockIdx.x >> 6, b = (blockIdx.x >> 3) & 7, h0 = (blockIdx.x & 7) * 4;

    if (wg == 2) {
        asm volatile("setmaxnreg.dec.sync.aligned.u32 24;");
        if (warp == 8 && lane == 0) {
            uint64_t pol;
            asm volatile("createpolicy.fractional.L2::evict_first.b64 %0, 1.0;" : "=l"(pol));
            int t = 0;
            for (int it = 0; it < 4; it++) {
                const int h = h0 + it;
                const int kvrow = (b * NH + h) * SK;
                for (int j = 0; j < PF_TILES; j++) {
                    const CUtensorMap* m = (j & 1) ? &maps.v[blk] : &maps.k[blk];
                    tma_prefetch_2d(m, 0, kvrow + (j >> 1) * 128);
                    tma_prefetch_2d(m, 64, kvrow + (j >> 1) * 128);
                }
                for (int i = 0; i < 24; i++, t++) {
                    const int st = t % NKV; const uint32_t ph = (t / NKV) & 1;
                    mbar_wait(bars + 8 * (NKV + st), ph ^ 1);
                    const uint32_t full = bars + 8 * st, dst = ring + st * TILE_BYTES;
                    mbar_expect_tx(full, TILE_BYTES);
                    if (i < 8) {
                        const int c = i >> 1;
                        const CUtensorMap* m; int c0, c1;
                        if (!(i & 1)) { m = &maps.x[blk]; c0 = c * 128; c1 = b * 128; }
                        else { m = &maps.wq[blk]; c0 = h * 128; c1 = c * 128; }
                        tma_load_2d(dst, m, full, c0, c1);
                        tma_load_2d(dst + HALF_BYTES, m, full, c0 + 64, c1);
                    } else {
                        const CUtensorMap* m = (i & 1) ? &maps.v[blk] : &maps.k[blk];
                        const int c1 = kvrow + ((i - 8) >> 1) * 128;
                        tma_load_2d_hint(dst, m, full, 0, c1, pol);
                        tma_load_2d_hint(dst + HALF_BYTES, m, full, 64, c1, pol);
                    }
                }
            }
        }
    } else {
        asm volatile("setmaxnreg.inc.sync.aligned.u32 240;");
        const int warp_in_wg = warp & 3;
        const bool elected = (tid & 127) == 0;
        const uint32_t stg = stg_base + wg * 16384;
        const float sl2 = 0.08838834764831845f * 1.4426950408889634f;
        float o[64], s[64];
        uint32_t p[32], q[32];
        int t = 0;
        for (int it = 0; it < 4; it++) {
            const int h = h0 + it;
#pragma unroll 1
            for (int c = 0; c < 4; c++) {
                const int sx = t % NKV, sw = (t + 1) % NKV;
                mbar_wait(bars + 8 * sx, (t / NKV) & 1);
                mbar_wait(bars + 8 * sw, ((t + 1) / NKV) & 1);
                const uint64_t da = make_desc(ring + sx * TILE_BYTES + wg * 8192, 16, 1024);
                const uint64_t db = make_desc(ring + sw * TILE_BYTES, HALF_BYTES, 1024);
                wgmma_fence();
#pragma unroll
                for (int kk = 0; kk < 8; kk++)
                    wgmma_ss<1>(s, da + (uint64_t)(((kk >> 2) * HALF_BYTES + (kk & 3) * 32) >> 4), db + (uint64_t)((kk * 2048) >> 4), (c | kk) != 0);
                wgmma_commit();
                wgmma_wait<0>();
                fence_acc(s);
                if (lane == 0) { mbar_arrive(bars + 8 * (NKV + sx)); mbar_arrive(bars + 8 * (NKV + sw)); }
                t += 2;
            }
#pragma unroll
            for (int i = 0; i < 32; i++) q[i] = pack_bf16(s[2 * i], s[2 * i + 1]);
            float m0, m1, l0, l1;
            {
                const int sk = t % NKV;
                mbar_wait(bars + 8 * sk, (t / NKV) & 1);
                const uint64_t db = make_desc(ring + sk * TILE_BYTES, 16, 1024);
                wgmma_fence();
#pragma unroll
                for (int kk = 0; kk < 8; kk++)
                    wgmma_rs<0>(s, q[4 * kk], q[4 * kk + 1], q[4 * kk + 2], q[4 * kk + 3], db + (uint64_t)(((kk >> 2) * HALF_BYTES + (kk & 3) * 32) >> 4), kk != 0);
                wgmma_commit();
                wgmma_wait<0>();
                fence_acc(s);
                if (lane == 0) mbar_arrive(bars + 8 * (NKV + sk));
                float mx0 = s[0], mx1 = s[2];
#pragma unroll
                for (int j = 0; j < 16; j++) {
                    mx0 = fmaxf(mx0, fmaxf(s[4 * j], s[4 * j + 1]));
                    mx1 = fmaxf(mx1, fmaxf(s[4 * j + 2], s[4 * j + 3]));
                }
                mx0 = fmaxf(mx0, __shfl_xor_sync(0xffffffffu, mx0, 1)); mx0 = fmaxf(mx0, __shfl_xor_sync(0xffffffffu, mx0, 2));
                mx1 = fmaxf(mx1, __shfl_xor_sync(0xffffffffu, mx1, 1)); mx1 = fmaxf(mx1, __shfl_xor_sync(0xffffffffu, mx1, 2));
                m0 = mx0; m1 = mx1;
                const float b0 = m0 * sl2, b1 = m1 * sl2;
                l0 = 0.f; l1 = 0.f;
#pragma unroll
                for (int j = 0; j < 16; j++) {
                    s[4 * j] = ex2(fmaf(s[4 * j], sl2, -b0)); s[4 * j + 1] = ex2(fmaf(s[4 * j + 1], sl2, -b0));
                    s[4 * j + 2] = ex2(fmaf(s[4 * j + 2], sl2, -b1)); s[4 * j + 3] = ex2(fmaf(s[4 * j + 3], sl2, -b1));
                    l0 += s[4 * j] + s[4 * j + 1]; l1 += s[4 * j + 2] + s[4 * j + 3];
                }
#pragma unroll
                for (int i = 0; i < 32; i++) p[i] = pack_bf16(s[2 * i], s[2 * i + 1]);
            }
#pragma unroll 1
            for (int j = 1; j < 8; j++) {
                const int tk = t + 2 * j, tv = t + 2 * j - 1;
                const int sk = tk % NKV, sv = tv % NKV;
                mbar_wait(bars + 8 * sk, (tk / NKV) & 1);
                const uint64_t dbk = make_desc(ring + sk * TILE_BYTES, 16, 1024);
                const uint64_t dbv = make_desc(ring + sv * TILE_BYTES, HALF_BYTES, 1024);
                wgmma_fence();
#pragma unroll
                for (int kk = 0; kk < 8; kk++)
                    wgmma_rs<0>(s, q[4 * kk], q[4 * kk + 1], q[4 * kk + 2], q[4 * kk + 3], dbk + (uint64_t)(((kk >> 2) * HALF_BYTES + (kk & 3) * 32) >> 4), kk != 0);
                wgmma_commit();
                mbar_wait(bars + 8 * sv, (tv / NKV) & 1);
#pragma unroll
                for (int kk = 0; kk < 8; kk++)
                    wgmma_rs<1>(o, p[4 * kk], p[4 * kk + 1], p[4 * kk + 2], p[4 * kk + 3], dbv + (uint64_t)((kk * 2048) >> 4), (j != 1) || (kk != 0));
                wgmma_commit();
                wgmma_wait<1>();
                fence_acc(s);
                if (lane == 0) mbar_arrive(bars + 8 * (NKV + sk));
                float mx0 = s[0], mx1 = s[2];
#pragma unroll
                for (int jj = 0; jj < 16; jj++) {
                    mx0 = fmaxf(mx0, fmaxf(s[4 * jj], s[4 * jj + 1]));
                    mx1 = fmaxf(mx1, fmaxf(s[4 * jj + 2], s[4 * jj + 3]));
                }
                mx0 = fmaxf(mx0, __shfl_xor_sync(0xffffffffu, mx0, 1)); mx0 = fmaxf(mx0, __shfl_xor_sync(0xffffffffu, mx0, 2));
                mx1 = fmaxf(mx1, __shfl_xor_sync(0xffffffffu, mx1, 1)); mx1 = fmaxf(mx1, __shfl_xor_sync(0xffffffffu, mx1, 2));
                const float mn0 = fmaxf(m0, mx0), mn1 = fmaxf(m1, mx1);
                const float a0 = ex2((m0 - mn0) * sl2), a1 = ex2((m1 - mn1) * sl2);
                m0 = mn0; m1 = mn1;
                const float b0 = m0 * sl2, b1 = m1 * sl2;
                float ps0 = 0.f, ps1 = 0.f;
#pragma unroll
                for (int jj = 0; jj < 16; jj++) {
                    s[4 * jj] = ex2(fmaf(s[4 * jj], sl2, -b0)); s[4 * jj + 1] = ex2(fmaf(s[4 * jj + 1], sl2, -b0));
                    s[4 * jj + 2] = ex2(fmaf(s[4 * jj + 2], sl2, -b1)); s[4 * jj + 3] = ex2(fmaf(s[4 * jj + 3], sl2, -b1));
                    ps0 += s[4 * jj] + s[4 * jj + 1]; ps1 += s[4 * jj + 2] + s[4 * jj + 3];
                }
                l0 = l0 * a0 + ps0; l1 = l1 * a1 + ps1;
                wgmma_wait<0>();
                fence_acc(o);
                fence_regs(p);
                if (lane == 0) mbar_arrive(bars + 8 * (NKV + sv));
#pragma unroll
                for (int jj = 0; jj < 16; jj++) {
                    o[4 * jj] *= a0; o[4 * jj + 1] *= a0; o[4 * jj + 2] *= a1; o[4 * jj + 3] *= a1;
                }
#pragma unroll
                for (int i = 0; i < 32; i++) p[i] = pack_bf16(s[2 * i], s[2 * i + 1]);
            }
            {
                const int tv = t + 15, sv = tv % NKV;
                mbar_wait(bars + 8 * sv, (tv / NKV) & 1);
                const uint64_t dbv = make_desc(ring + sv * TILE_BYTES, HALF_BYTES, 1024);
                wgmma_fence();
#pragma unroll
                for (int kk = 0; kk < 8; kk++)
                    wgmma_rs<1>(o, p[4 * kk], p[4 * kk + 1], p[4 * kk + 2], p[4 * kk + 3], dbv + (uint64_t)((kk * 2048) >> 4), 1);
                wgmma_commit();
                wgmma_wait<0>();
                fence_acc(o);
                fence_regs(p);
                if (lane == 0) mbar_arrive(bars + 8 * (NKV + sv));
            }
            t += 16;
            l0 += __shfl_xor_sync(0xffffffffu, l0, 1); l0 += __shfl_xor_sync(0xffffffffu, l0, 2);
            l1 += __shfl_xor_sync(0xffffffffu, l1, 1); l1 += __shfl_xor_sync(0xffffffffu, l1, 2);
            store_tile(o, 1.0f / l0, 1.0f / l1, stg, &maps.o, h * 128, (blk * NB + b) * SQ + wg * 64, 1 + wg, lane, warp_in_wg, elected);
        }
        if (elected) bulk_wait0();
    }
}

struct Maps2 {
    CUtensorMap o, wo[2], out;
};
constexpr int ST2_BYTES = TILE_BYTES + HALF_BYTES;
constexpr int NS2B = 4;

__global__ void __launch_bounds__(384, 1) oproj_kernel(const __grid_constant__ Maps2 maps) {
    extern __shared__ uint8_t smem_raw[];
    const uint32_t ring = (smem_u32(smem_raw) + 1023u) & ~1023u;
    const uint32_t stg_base = ring + NS2B * ST2_BYTES;
    const uint32_t bars = stg_base + 16384;
    const int tid = threadIdx.x, wg = tid >> 7, lane = tid & 31, warp = tid >> 5;
    const int nt = blockIdx.x & 7, rt = (blockIdx.x >> 3) & 7, blk = blockIdx.x >> 6;
    if (tid == 0) {
        for (int s = 0; s < NS2B; s++) { mbar_init(bars + 8 * s, 1); mbar_init(bars + 8 * (NS2B + s), 8); }
        asm volatile("fence.mbarrier_init.release.cluster;" ::: "memory");
    }
    __syncthreads();
    if (wg == 2) {
        asm volatile("setmaxnreg.dec.sync.aligned.u32 24;");
        if (warp == 8 && lane == 0) {
            for (int c = 0; c < 32; c++) {
                const int st = c % NS2B;
                mbar_wait(bars + 8 * (NS2B + st), ((c / NS2B) & 1) ^ 1);
                const uint32_t full = bars + 8 * st, dst = ring + st * ST2_BYTES;
                mbar_expect_tx(full, ST2_BYTES);
                tma_load_2d(dst, &maps.o, full, c * 128, (blk * NB + rt) * SQ);
                tma_load_2d(dst + HALF_BYTES, &maps.o, full, c * 128 + 64, (blk * NB + rt) * SQ);
                tma_load_2d(dst + TILE_BYTES, &maps.wo[blk], full, nt * 64, c * 128);
            }
        }
    } else {
        asm volatile("setmaxnreg.inc.sync.aligned.u32 240;");
        const int warp_in_wg = warp & 3;
        float acc[32];
#pragma unroll 1
        for (int c = 0; c < 32; c++) {
            const int st = c % NS2B;
            mbar_wait(bars + 8 * st, (c / NS2B) & 1);
            const uint64_t da = make_desc(ring + st * ST2_BYTES + wg * 8192, 16, 1024);
            const uint64_t db = make_desc(ring + st * ST2_BYTES + TILE_BYTES, HALF_BYTES, 1024);
            wgmma_fence();
#pragma unroll
            for (int kk = 0; kk < 8; kk++)
                wgmma_ss_n64(acc, da + (uint64_t)(((kk >> 2) * HALF_BYTES + (kk & 3) * 32) >> 4), db + (uint64_t)((kk * 2048) >> 4), (c | kk) != 0);
            wgmma_commit();
            wgmma_wait<0>();
#pragma unroll
            for (int i = 0; i < 32; i++) asm volatile("" : "+f"(acc[i])::"memory");
            if (lane == 0) mbar_arrive(bars + 8 * (NS2B + st));
        }
        const uint32_t stg = stg_base + wg * 8192;
        const int mi = lane >> 3, row = warp_in_wg * 16 + (mi & 1) * 8 + (lane & 7);
#pragma unroll
        for (int j = 0; j < 8; j += 2) {
            const int c = j + (mi >> 1);
            stmatrix_x4(stg + row * 128 + ((c ^ (row & 7)) << 4), pack_bf16(acc[4 * j], acc[4 * j + 1]), pack_bf16(acc[4 * j + 2], acc[4 * j + 3]),
                        pack_bf16(acc[4 * j + 4], acc[4 * j + 5]), pack_bf16(acc[4 * j + 6], acc[4 * j + 7]));
        }
        fence_proxy_async();
        named_bar_sync(1 + wg, 128);
        if ((tid & 127) == 0) {
            tma_store_2d(&maps.out, stg, blk * 512 + nt * 64, rt * SQ + wg * 64);
            bulk_commit();
            bulk_wait0();
        }
    }
}

typedef CUresult (*PFN_tmEncodeTiled)(CUtensorMap*, CUtensorMapDataType, cuuint32_t, void*, const cuuint64_t*, const cuuint64_t*,
                                      const cuuint32_t*, const cuuint32_t*, CUtensorMapInterleave, CUtensorMapSwizzle,
                                      CUtensorMapL2promotion, CUtensorMapFloatOOBfill);

void make_map(PFN_tmEncodeTiled enc, CUtensorMap* m, const void* ptr, uint64_t rows, uint64_t cols, uint32_t box_rows) {
    cuuint64_t dims[2] = {cols, rows};
    cuuint64_t strides[1] = {cols * 2};
    cuuint32_t box[2] = {64, box_rows};
    cuuint32_t estr[2] = {1, 1};
    enc(m, CU_TENSOR_MAP_DATA_TYPE_BFLOAT16, 2, const_cast<void*>(ptr), dims, strides, box, estr, CU_TENSOR_MAP_INTERLEAVE_NONE,
        CU_TENSOR_MAP_SWIZZLE_128B, CU_TENSOR_MAP_L2_PROMOTION_L2_256B, CU_TENSOR_MAP_FLOAT_OOB_FILL_NONE);
}

}

extern "C" void kernel_launch(void* const* d_in, const int* in_sizes, int n_in, void* d_out, int out_size) {
    (void)in_sizes; (void)n_in; (void)out_size;
    void* fn = nullptr;
    cudaDriverEntryPointQueryResult qres;
    cudaGetDriverEntryPoint("cuTensorMapEncodeTiled", &fn, cudaEnableDefault, &qres);
    PFN_tmEncodeTiled enc = (PFN_tmEncodeTiled)fn;
    void* o_scr = nullptr;
    cudaGetSymbolAddress(&o_scr, g_o_scratch);

    Maps1 m1; Maps2 m2;
    for (int blk = 0; blk < 2; blk++) {
        make_map(enc, &m1.x[blk], d_in[blk * 5 + 0], ROWS, DM, 128);
        make_map(enc, &m1.k[blk], d_in[blk * 5 + 1], (uint64_t)NB * NH * SK, DH, 128);
        make_map(enc, &m1.v[blk], d_in[blk * 5 + 2], (uint64_t)NB * NH * SK, DH, 128);
        make_map(enc, &m1.wq[blk], d_in[blk * 5 + 3], DM, HD, 128);
        make_map(enc, &m2.wo[blk], d_in[blk * 5 + 4], HD, DM, 128);
    }
    make_map(enc, &m1.o, o_scr, 2 * ROWS, HD, 64);
    make_map(enc, &m2.o, o_scr, 2 * ROWS, HD, 128);
    make_map(enc, &m2.out, d_out, ROWS, 2 * DM, 64);

    const int smem1 = NKV * TILE_BYTES + STG_BYTES + 1024 + 256;
    const int smem2 = NS2B * ST2_BYTES + 16384 + 1024 + 256;
    cudaFuncSetAttribute(attn_kernel, cudaFuncAttributeMaxDynamicSharedMemorySize, smem1);
    cudaFuncSetAttribute(oproj_kernel, cudaFuncAttributeMaxDynamicSharedMemorySize, smem2);
    int dev = 0, nsm = 132;
    cudaGetDevice(&dev);
    cudaDeviceGetAttribute(&nsm, cudaDevAttrMultiProcessorCount, dev);
    (void)nsm;
    attn_kernel<<<128, 384, smem1>>>(m1);
    oproj_kernel<<<128, 384, smem2>>>(m2);
}
```
